```python
import torch

def _softmax(x, axis=-1):
    return torch.softmax(x, dim=axis)
def _gelu(x):
    return torch.nn.functional.gelu(x, approximate="tanh")
def _silu(x):
    return torch.nn.functional.silu(x)
def _sigmoid(x):
    return torch.sigmoid(x)
def _layernorm(x, axis=-1, eps=1e-5):
    m = x.mean(dim=axis, keepdim=True)
    v = x.var(dim=axis, keepdim=True, unbiased=False)
    return (x - m) / torch.sqrt(v + eps)
def _scatter_add(tgt, idx, src, axis=0):
    return tgt.clone().index_add_(axis, idx, src)
def _segment_sum(src, seg, n):
    out = torch.zeros((n,) + src.shape[1:], dtype=src.dtype)
    return out.index_add_(0, seg, src)
def _pad(x, pw):
    flat = tuple(v for pair in reversed(pw) for v in pair)
    return torch.nn.functional.pad(x, flat)

kernel_name = 'gated_mix__sliding_block__dense_activation_mish__prompt'

def setup_inputs():

    _w = (lambda a: (lambda t: t.to(torch.bfloat16) if t.is_floating_point() else t)(torch.as_tensor(a)))
    def _A_setup():
        B, S, D = 1, 2048, 512
        return {
            "x": _w((lambda *s: torch.randn(*s, dtype=torch.bfloat16) * 0.05)(B, S, D)),
            "wqkv": _w((lambda *s: torch.randn(*s, dtype=torch.bfloat16) * 0.8)(D, 3 * D)),
            "wo": _w((lambda *s: torch.randn(*s, dtype=torch.bfloat16) * 0.05)(D, D)),
        }
    _A_in = _A_setup()

    def _B_setup():
        B, S, D, F = 1, 2048, 512, 1376
        return {
            "x": _w((lambda *s: torch.randn(*s, dtype=torch.bfloat16) * 0.05)(B, S, D)),
            "w1": _w((lambda *s: torch.randn(*s, dtype=torch.bfloat16) * 12.8)(D, F) * (D ** -0.5)),
            "b1": _w((lambda *s: torch.randn(*s, dtype=torch.bfloat16) * 0.8)(F)),
            "w2": _w((lambda *s: torch.randn(*s, dtype=torch.bfloat16) * 0.8)(F, D) * (F ** -0.5)),
        }
    _B_in = _B_setup()

    return {
        "A_x": _A_in["x"],
        "A_wqkv": _A_in["wqkv"],
        "A_wo": _A_in["wo"],
        "B_x": _B_in["x"],
        "B_w1": _B_in["w1"],
        "B_b1": _B_in["b1"],
        "B_w2": _B_in["w2"],
        "gate_w": _w((lambda *s: torch.randn(*s, dtype=torch.bfloat16) * 0.05)(512) * 16.0),
    }

def reference(A_x, A_wqkv, A_wo, B_x, B_w1, B_b1, B_w2, gate_w):
    def _A_ref(x, wqkv, wo):
        B, S, D = x.shape
        H = 32; Dh = D // H; W = 256
        qkv = (lambda x, *d: x.permute(*d))((x @ wqkv).reshape(B, S, 3, H, Dh), 2, 0, 3, 1, 4)
        q, k, v = qkv[0], qkv[1], qkv[2]
        scores = torch.einsum("bhqd,bhkd->bhqk", q, k) * (Dh ** -0.5)
        idx = torch.arange(S)
        mask = (idx[:, None] - idx[None, :] >= 0) & (idx[:, None] - idx[None, :] < W)
        scores = torch.where(mask[None, None], scores, -1e9)
        p = _softmax(scores, axis=-1)
        o = torch.einsum("bhqk,bhkd->bhqd", p, v)
        return (lambda x, *d: x.permute(*d))(o, 0, 2, 1, 3).reshape(B, S, D) @ wo

    def _B_ref(x, w1, b1, w2):
        h = torch.einsum("bsd,df->bsf", x, w1) + b1
        sp = torch.log1p(torch.exp(-torch.abs(h))) + torch.where(h > 0, h, torch.zeros_like(h))
        act = h * torch.tanh(sp)
        return torch.einsum("bsf,fd->bsd", act, w2)

    x = A_x
    g = _sigmoid((x * gate_w).sum(-1, keepdims=True))
    a = _A_ref(x, A_wqkv, A_wo)
    b = _B_ref(x, B_w1, B_b1, B_w2)
    return g * a + (1 - g) * b
```

```cpp
#include <cuda_runtime.h>
#include <cuda_bf16.h>
#include <cuda.h>
#include <stdint.h>

typedef __nv_bfloat16 bf16;

constexpr int SEQ = 2048, DM = 512, FF = 1376;
constexpr int NCTA = 128;

__device__ __align__(1024) bf16 g_kvo[SEQ * 1536];
__device__ __align__(1024) bf16 g_act[SEQ * FF];
__device__ float g_gate[SEQ];
__device__ unsigned g_oflag[16 * 8];
__device__ unsigned g_kvflag[16 * 8];
__device__ float g_knorm[16 * 8 * 4];
__device__ unsigned g_actcnt[16];
__device__ unsigned g_epoch;
__device__ unsigned g_done;

#define TS(i) do {} while (0)
__device__ __forceinline__ uint32_t smem_u32(const void* p) { return (uint32_t)__cvta_generic_to_shared(p); }

__device__ __forceinline__ void mbar_init(uint32_t bar, uint32_t cnt) {
  asm volatile("mbarrier.init.shared::cta.b64 [%0], %1;" ::"r"(bar), "r"(cnt) : "memory");
}
__device__ __forceinline__ void mbar_arrive(uint32_t bar) {
  asm volatile("mbarrier.arrive.shared::cta.b64 _, [%0];" ::"r"(bar) : "memory");
}
__device__ __forceinline__ void mbar_expect_tx(uint32_t bar, uint32_t bytes) {
  asm volatile("mbarrier.arrive.expect_tx.shared::cta.b64 _, [%0], %1;" ::"r"(bar), "r"(bytes) : "memory");
}
__device__ __forceinline__ bool mbar_try(uint32_t bar, uint32_t parity) {
  uint32_t ok;
  asm volatile("{\n.reg .pred p;\nmbarrier.try_wait.parity.shared::cta.b64 p, [%1], %2;\nselp.u32 %0, 1, 0, p;\n}\n"
               : "=r"(ok) : "r"(bar), "r"(parity) : "memory");
  return ok != 0;
}
__device__ __forceinline__ void mbar_wait(uint32_t bar, uint32_t parity) {
  uint32_t n = 0;
  while (!mbar_try(bar, parity)) {
    if (++n > (1u << 22)) break;
  }
}
__device__ __forceinline__ unsigned ld_acquire(const unsigned* p) {
  unsigned v;
  asm volatile("ld.acquire.gpu.global.u32 %0, [%1];" : "=r"(v) : "l"(p) : "memory");
  return v;
}
__device__ __forceinline__ void st_release(unsigned* p, unsigned v) {
  asm volatile("st.release.gpu.global.u32 [%0], %1;" ::"l"(p), "r"(v) : "memory");
}
__device__ __forceinline__ void red_release_add(unsigned* p, unsigned v) {
  asm volatile("red.release.gpu.global.add.u32 [%0], %1;" ::"l"(p), "r"(v) : "memory");
}
__device__ __forceinline__ void spin_ge(const unsigned* p, unsigned target) {
  uint32_t n = 0;
  while ((int)(ld_acquire(p) - target) < 0) {
    __nanosleep(20);
    if (++n > (1u << 22)) __trap();
  }
}
__device__ __forceinline__ void fence_proxy_async() { asm volatile("fence.proxy.async;" ::: "memory"); }
__device__ __forceinline__ void fence_proxy_async_smem() { asm volatile("fence.proxy.async.shared::cta;" ::: "memory"); }

__device__ __forceinline__ void tma_load_2d(uint32_t dst, const CUtensorMap* tm, int c0, int c1, uint32_t bar) {
  asm volatile("cp.async.bulk.tensor.2d.shared::cluster.global.mbarrier::complete_tx::bytes [%0], [%1, {%3, %4}], [%2];"
               ::"r"(dst), "l"(tm), "r"(bar), "r"(c0), "r"(c1) : "memory");
}
__device__ __forceinline__ void tma_store_2d(const CUtensorMap* tm, uint32_t src, int c0, int c1) {
  asm volatile("cp.async.bulk.tensor.2d.global.shared::cta.bulk_group [%0, {%2, %3}], [%1];"
               ::"l"(tm), "r"(src), "r"(c0), "r"(c1) : "memory");
}
__device__ __forceinline__ void l2_prefetch(const void* p, uint32_t bytes) {
  asm volatile("cp.async.bulk.prefetch.L2.global [%0], %1;" ::"l"(p), "r"(bytes) : "memory");
}
__device__ __forceinline__ void bulk_commit() { asm volatile("cp.async.bulk.commit_group;" ::: "memory"); }
__device__ __forceinline__ void bulk_wait0() { asm volatile("cp.async.bulk.wait_group 0;" ::: "memory"); }
__device__ __forceinline__ void prefetch_tm(const CUtensorMap* tm) {
  asm volatile("prefetch.tensormap [%0];" ::"l"(tm) : "memory");
}

__device__ __forceinline__ void wgmma_fence() { asm volatile("wgmma.fence.sync.aligned;" ::: "memory"); }
__device__ __forceinline__ void wgmma_commit() { asm volatile("wgmma.commit_group.sync.aligned;" ::: "memory"); }
template <int N> __device__ __forceinline__ void wgmma_wait() { asm volatile("wgmma.wait_group.sync.aligned %0;" ::"n"(N) : "memory"); }

__device__ __forceinline__ uint64_t desc_kmajor(uint32_t addr) {
  return (uint64_t)((addr & 0x3FFFF) >> 4) | (1ull << 16) | (64ull << 32) | (1ull << 62);
}
__device__ __forceinline__ uint64_t desc_mnmajor(uint32_t addr) {
  return (uint64_t)((addr & 0x3FFFF) >> 4) | (512ull << 16) | (64ull << 32) | (1ull << 62);
}

__device__ __forceinline__ void wgmma_n192(float (&d)[96], uint64_t da, uint64_t db, int scale_d) {
  asm volatile("{\n.reg .pred p;\nsetp.ne.b32 p, %98, 0;\n"
    "wgmma.mma_async.sync.aligned.m64n192k16.f32.bf16.bf16 {%0, %1, %2, %3, %4, %5, %6, %7, %8, %9, %10, %11, %12, %13, %14, %15, %16, %17, %18, %19, %20, %21, %22, %23, %24, %25, %26, %27, %28, %29, %30, %31, %32, %33, %34, %35, %36, %37, %38, %39, %40, %41, %42, %43, %44, %45, %46, %47, %48, %49, %50, %51, %52, %53, %54, %55, %56, %57, %58, %59, %60, %61, %62, %63, %64, %65, %66, %67, %68, %69, %70, %71, %72, %73, %74, %75, %76, %77, %78, %79, %80, %81, %82, %83, %84, %85, %86, %87, %88, %89, %90, %91, %92, %93, %94, %95}, %96, %97, p, 1, 1, 0, 1;\n}\n"
    : "+f"(d[0]), "+f"(d[1]), "+f"(d[2]), "+f"(d[3]), "+f"(d[4]), "+f"(d[5]), "+f"(d[6]), "+f"(d[7]), "+f"(d[8]), "+f"(d[9]), "+f"(d[10]), "+f"(d[11]), "+f"(d[12]), "+f"(d[13]), "+f"(d[14]), "+f"(d[15]), "+f"(d[16]), "+f"(d[17]), "+f"(d[18]), "+f"(d[19]), "+f"(d[20]), "+f"(d[21]), "+f"(d[22]), "+f"(d[23]), "+f"(d[24]), "+f"(d[25]), "+f"(d[26]), "+f"(d[27]), "+f"(d[28]), "+f"(d[29]), "+f"(d[30]), "+f"(d[31]), "+f"(d[32]), "+f"(d[33]), "+f"(d[34]), "+f"(d[35]), "+f"(d[36]), "+f"(d[37]), "+f"(d[38]), "+f"(d[39]), "+f"(d[40]), "+f"(d[41]), "+f"(d[42]), "+f"(d[43]), "+f"(d[44]), "+f"(d[45]), "+f"(d[46]), "+f"(d[47]), "+f"(d[48]), "+f"(d[49]), "+f"(d[50]), "+f"(d[51]), "+f"(d[52]), "+f"(d[53]), "+f"(d[54]), "+f"(d[55]), "+f"(d[56]), "+f"(d[57]), "+f"(d[58]), "+f"(d[59]), "+f"(d[60]), "+f"(d[61]), "+f"(d[62]), "+f"(d[63]), "+f"(d[64]), "+f"(d[65]), "+f"(d[66]), "+f"(d[67]), "+f"(d[68]), "+f"(d[69]), "+f"(d[70]), "+f"(d[71]), "+f"(d[72]), "+f"(d[73]), "+f"(d[74]), "+f"(d[75]), "+f"(d[76]), "+f"(d[77]), "+f"(d[78]), "+f"(d[79]), "+f"(d[80]), "+f"(d[81]), "+f"(d[82]), "+f"(d[83]), "+f"(d[84]), "+f"(d[85]), "+f"(d[86]), "+f"(d[87]), "+f"(d[88]), "+f"(d[89]), "+f"(d[90]), "+f"(d[91]), "+f"(d[92]), "+f"(d[93]), "+f"(d[94]), "+f"(d[95])
    : "l"(da), "l"(db), "r"(scale_d));
}

__device__ __forceinline__ void wgmma_n176(float (&d)[88], uint64_t da, uint64_t db, int scale_d) {
  asm volatile("{\n.reg .pred p;\nsetp.ne.b32 p, %90, 0;\n"
    "wgmma.mma_async.sync.aligned.m64n176k16.f32.bf16.bf16 {%0, %1, %2, %3, %4, %5, %6, %7, %8, %9, %10, %11, %12, %13, %14, %15, %16, %17, %18, %19, %20, %21, %22, %23, %24, %25, %26, %27, %28, %29, %30, %31, %32, %33, %34, %35, %36, %37, %38, %39, %40, %41, %42, %43, %44, %45, %46, %47, %48, %49, %50, %51, %52, %53, %54, %55, %56, %57, %58, %59, %60, %61, %62, %63, %64, %65, %66, %67, %68, %69, %70, %71, %72, %73, %74, %75, %76, %77, %78, %79, %80, %81, %82, %83, %84, %85, %86, %87}, %88, %89, p, 1, 1, 0, 1;\n}\n"
    : "+f"(d[0]), "+f"(d[1]), "+f"(d[2]), "+f"(d[3]), "+f"(d[4]), "+f"(d[5]), "+f"(d[6]), "+f"(d[7]), "+f"(d[8]), "+f"(d[9]), "+f"(d[10]), "+f"(d[11]), "+f"(d[12]), "+f"(d[13]), "+f"(d[14]), "+f"(d[15]), "+f"(d[16]), "+f"(d[17]), "+f"(d[18]), "+f"(d[19]), "+f"(d[20]), "+f"(d[21]), "+f"(d[22]), "+f"(d[23]), "+f"(d[24]), "+f"(d[25]), "+f"(d[26]), "+f"(d[27]), "+f"(d[28]), "+f"(d[29]), "+f"(d[30]), "+f"(d[31]), "+f"(d[32]), "+f"(d[33]), "+f"(d[34]), "+f"(d[35]), "+f"(d[36]), "+f"(d[37]), "+f"(d[38]), "+f"(d[39]), "+f"(d[40]), "+f"(d[41]), "+f"(d[42]), "+f"(d[43]), "+f"(d[44]), "+f"(d[45]), "+f"(d[46]), "+f"(d[47]), "+f"(d[48]), "+f"(d[49]), "+f"(d[50]), "+f"(d[51]), "+f"(d[52]), "+f"(d[53]), "+f"(d[54]), "+f"(d[55]), "+f"(d[56]), "+f"(d[57]), "+f"(d[58]), "+f"(d[59]), "+f"(d[60]), "+f"(d[61]), "+f"(d[62]), "+f"(d[63]), "+f"(d[64]), "+f"(d[65]), "+f"(d[66]), "+f"(d[67]), "+f"(d[68]), "+f"(d[69]), "+f"(d[70]), "+f"(d[71]), "+f"(d[72]), "+f"(d[73]), "+f"(d[74]), "+f"(d[75]), "+f"(d[76]), "+f"(d[77]), "+f"(d[78]), "+f"(d[79]), "+f"(d[80]), "+f"(d[81]), "+f"(d[82]), "+f"(d[83]), "+f"(d[84]), "+f"(d[85]), "+f"(d[86]), "+f"(d[87])
    : "l"(da), "l"(db), "r"(scale_d));
}

__device__ __forceinline__ void wgmma_n64(float (&d)[32], uint64_t da, uint64_t db, int scale_d) {
  asm volatile("{\n.reg .pred p;\nsetp.ne.b32 p, %34, 0;\n"
    "wgmma.mma_async.sync.aligned.m64n64k16.f32.bf16.bf16 {%0, %1, %2, %3, %4, %5, %6, %7, %8, %9, %10, %11, %12, %13, %14, %15, %16, %17, %18, %19, %20, %21, %22, %23, %24, %25, %26, %27, %28, %29, %30, %31}, %32, %33, p, 1, 1, 0, 1;\n}\n"
    : "+f"(d[0]), "+f"(d[1]), "+f"(d[2]), "+f"(d[3]), "+f"(d[4]), "+f"(d[5]), "+f"(d[6]), "+f"(d[7]), "+f"(d[8]), "+f"(d[9]), "+f"(d[10]), "+f"(d[11]), "+f"(d[12]), "+f"(d[13]), "+f"(d[14]), "+f"(d[15]), "+f"(d[16]), "+f"(d[17]), "+f"(d[18]), "+f"(d[19]), "+f"(d[20]), "+f"(d[21]), "+f"(d[22]), "+f"(d[23]), "+f"(d[24]), "+f"(d[25]), "+f"(d[26]), "+f"(d[27]), "+f"(d[28]), "+f"(d[29]), "+f"(d[30]), "+f"(d[31])
    : "l"(da), "l"(db), "r"(scale_d));
}

__device__ __forceinline__ void wgmma_n128_ta(float (&d)[64], uint64_t da, uint64_t db, int scale_d) {
  asm volatile("{\n.reg .pred p;\nsetp.ne.b32 p, %66, 0;\n"
    "wgmma.mma_async.sync.aligned.m64n128k16.f32.bf16.bf16 {%0, %1, %2, %3, %4, %5, %6, %7, %8, %9, %10, %11, %12, %13, %14, %15, %16, %17, %18, %19, %20, %21, %22, %23, %24, %25, %26, %27, %28, %29, %30, %31, %32, %33, %34, %35, %36, %37, %38, %39, %40, %41, %42, %43, %44, %45, %46, %47, %48, %49, %50, %51, %52, %53, %54, %55, %56, %57, %58, %59, %60, %61, %62, %63}, %64, %65, p, 1, 1, 1, 0;\n}\n"
    : "+f"(d[0]), "+f"(d[1]), "+f"(d[2]), "+f"(d[3]), "+f"(d[4]), "+f"(d[5]), "+f"(d[6]), "+f"(d[7]), "+f"(d[8]), "+f"(d[9]), "+f"(d[10]), "+f"(d[11]), "+f"(d[12]), "+f"(d[13]), "+f"(d[14]), "+f"(d[15]), "+f"(d[16]), "+f"(d[17]), "+f"(d[18]), "+f"(d[19]), "+f"(d[20]), "+f"(d[21]), "+f"(d[22]), "+f"(d[23]), "+f"(d[24]), "+f"(d[25]), "+f"(d[26]), "+f"(d[27]), "+f"(d[28]), "+f"(d[29]), "+f"(d[30]), "+f"(d[31]), "+f"(d[32]), "+f"(d[33]), "+f"(d[34]), "+f"(d[35]), "+f"(d[36]), "+f"(d[37]), "+f"(d[38]), "+f"(d[39]), "+f"(d[40]), "+f"(d[41]), "+f"(d[42]), "+f"(d[43]), "+f"(d[44]), "+f"(d[45]), "+f"(d[46]), "+f"(d[47]), "+f"(d[48]), "+f"(d[49]), "+f"(d[50]), "+f"(d[51]), "+f"(d[52]), "+f"(d[53]), "+f"(d[54]), "+f"(d[55]), "+f"(d[56]), "+f"(d[57]), "+f"(d[58]), "+f"(d[59]), "+f"(d[60]), "+f"(d[61]), "+f"(d[62]), "+f"(d[63])
    : "l"(da), "l"(db), "r"(scale_d));
}

__device__ __forceinline__ uint32_t pack_bf16(float lo, float hi) {
  uint32_t r;
  asm("cvt.rn.bf16x2.f32 %0, %1, %2;" : "=r"(r) : "f"(hi), "f"(lo));
  return r;
}
__device__ __forceinline__ float bf_lo(uint32_t v) { return __uint_as_float(v << 16); }
__device__ __forceinline__ float bf_hi(uint32_t v) { return __uint_as_float(v & 0xffff0000u); }
__device__ __forceinline__ float bf16r(float x) { return __bfloat162float(__float2bfloat16_rn(x)); }
__device__ __forceinline__ float ex2(float x) { float y; asm("ex2.approx.ftz.f32 %0, %1;" : "=f"(y) : "f"(x)); return y; }
__device__ __forceinline__ float rcp(float x) { float y; asm("rcp.approx.ftz.f32 %0, %1;" : "=f"(y) : "f"(x)); return y; }

__device__ __forceinline__ void stmatrix_x4(uint32_t addr, uint32_t r0, uint32_t r1, uint32_t r2, uint32_t r3) {
  asm volatile("stmatrix.sync.aligned.m8n8.x4.shared.b16 [%0], {%1, %2, %3, %4};"
               ::"r"(addr), "r"(r0), "r"(r1), "r"(r2), "r"(r3) : "memory");
}
__device__ __forceinline__ void stmatrix_x4_t(uint32_t addr, uint32_t r0, uint32_t r1, uint32_t r2, uint32_t r3) {
  asm volatile("stmatrix.sync.aligned.m8n8.x4.trans.shared.b16 [%0], {%1, %2, %3, %4};"
               ::"r"(addr), "r"(r0), "r"(r1), "r"(r2), "r"(r3) : "memory");
}
__device__ __forceinline__ void ldmatrix_x4(uint32_t addr, uint32_t& r0, uint32_t& r1, uint32_t& r2, uint32_t& r3) {
  asm volatile("ldmatrix.sync.aligned.m8n8.x4.shared.b16 {%0, %1, %2, %3}, [%4];"
               : "=r"(r0), "=r"(r1), "=r"(r2), "=r"(r3) : "r"(addr) : "memory");
}
__device__ __forceinline__ void ldmatrix_x4_t(uint32_t addr, uint32_t& r0, uint32_t& r1, uint32_t& r2, uint32_t& r3) {
  asm volatile("ldmatrix.sync.aligned.m8n8.x4.trans.shared.b16 {%0, %1, %2, %3}, [%4];"
               : "=r"(r0), "=r"(r1), "=r"(r2), "=r"(r3) : "r"(addr) : "memory");
}
__device__ __forceinline__ void mma16816(float* c, uint32_t a0, uint32_t a1, uint32_t a2, uint32_t a3, uint32_t b0, uint32_t b1) {
  asm volatile("mma.sync.aligned.m16n8k16.row.col.f32.bf16.bf16.f32 {%0,%1,%2,%3}, {%4,%5,%6,%7}, {%8,%9}, {%0,%1,%2,%3};"
               : "+f"(c[0]), "+f"(c[1]), "+f"(c[2]), "+f"(c[3])
               : "r"(a0), "r"(a1), "r"(a2), "r"(a3), "r"(b0), "r"(b1));
}
__device__ __forceinline__ void named_bar_sync(int id, int n) { asm volatile("bar.sync %0, %1;" ::"r"(id), "r"(n) : "memory"); }

constexpr uint32_t SM_X = 0;
constexpr uint32_t SM_RING = 131072;
constexpr uint32_t SM_BAR = 229376;
constexpr uint32_t SM_B1 = 229376 + 352;
constexpr uint32_t SM_CTR = 229376 + 1088;
constexpr uint32_t SM_KN = 229376 + 1104;
constexpr uint32_t SM_TOTAL = 229376 + 2112;
constexpr uint32_t STAGE_BYTES = 24576;

constexpr int B_XFULL = 0;
constexpr int B_WFULL = 8;
constexpr int B_WEMPTY = 12;
constexpr int B_DFULL = 16;
constexpr int B_KVFULL = 24;
constexpr int B_GATE = 25;
constexpr int B_QKVST = 29;
constexpr int B_OST = 30;
constexpr int B_ACTDONE = 31;
constexpr int B_OFULL = 32;
constexpr int B_WOFULL = 40;
constexpr int B_KVST = 27;
constexpr int B_XFREE = 28;
constexpr int B_HST = 26;

__device__ __forceinline__ int chunk_start(int j) { return j < 6 ? j * 176 : 1056 + (j - 6) * 160; }
__device__ __forceinline__ int chunk_len(int j) { return j < 6 ? 176 : 160; }

__device__ __forceinline__ void finish_max(float (&m)[2]) {
  const float C = 0.25f * 1.4426950408889634f;
#pragma unroll
  for (int r = 0; r < 2; r++) {
    float v = m[r];
    v = fmaxf(v, __shfl_xor_sync(0xffffffffu, v, 1));
    v = fmaxf(v, __shfl_xor_sync(0xffffffffu, v, 2));
    m[r] = -v * C;
  }
}
__device__ __forceinline__ void store_o(uint32_t Qb, int t, int h, int lane, const float (&o)[8], const float (&sum)[2]) {
  const int g = lane >> 2, tq = lane & 3;
  const int row = 16 * t + g;
  const uint32_t a = Qb + row * 128 + tq * 4;
  const uint32_t sw = (uint32_t)(row & 7);
  const float r0 = 1.0f / sum[0], r1 = 1.0f / sum[1];
  const int c2 = 2 * h;
  uint32_t w00 = pack_bf16(o[0] * r0, o[1] * r0), w01 = pack_bf16(o[4] * r0, o[5] * r0);
  uint32_t w10 = pack_bf16(o[2] * r1, o[3] * r1), w11 = pack_bf16(o[6] * r1, o[7] * r1);
  asm volatile("st.shared.b32 [%0], %1;" ::"r"(a + ((c2 ^ sw) << 4)), "r"(w00) : "memory");
  asm volatile("st.shared.b32 [%0], %1;" ::"r"(a + (((c2 + 1) ^ sw) << 4)), "r"(w01) : "memory");
  asm volatile("st.shared.b32 [%0], %1;" ::"r"(a + 1024 + ((c2 ^ sw) << 4)), "r"(w10) : "memory");
  asm volatile("st.shared.b32 [%0], %1;" ::"r"(a + 1024 + (((c2 + 1) ^ sw) << 4)), "r"(w11) : "memory");
}
__device__ __forceinline__ uint32_t KBLK(uint32_t sm, int blk) {
  return sm + SM_X + (uint32_t)(blk & 7) * 2048u + (blk >= 16 ? 0u : (blk >= 8 ? 3u : 4u) * 16384u);
}
__device__ __forceinline__ uint32_t VBLK(uint32_t sm, int blk) {
  return sm + SM_X + (uint32_t)(blk & 7) * 2048u + (blk >= 16 ? 1u : (blk >= 8 ? 5u : 6u)) * 16384u;
}
template <int MODE>
__device__ __forceinline__ void qk_frag(float (&s)[8], const uint32_t (&q)[4], uint32_t k0, uint32_t k1, uint32_t k2, uint32_t k3, int lane) {
#pragma unroll
  for (int i = 0; i < 8; i++) s[i] = 0.f;
  mma16816(&s[0], q[0], q[1], q[2], q[3], k0, k1);
  mma16816(&s[4], q[0], q[1], q[2], q[3], k2, k3);
  if (MODE > 0) {
    const int g = lane >> 2, tq = lane & 3;
#pragma unroll
    for (int i = 0; i < 8; i++) {
      const int c = (i >> 2) * 8 + 2 * tq + (i & 1);
      const int r = g + ((i >> 1) & 1) * 8;
      const bool ok = (MODE == 1) ? (c > r) : (c <= r);
      if (!ok) s[i] = -INFINITY;
    }
  }
}
__device__ __forceinline__ void upd_max(float (&m)[2], const float (&s)[8]) {
  m[0] = fmaxf(m[0], fmaxf(fmaxf(s[0], s[1]), fmaxf(s[4], s[5])));
  m[1] = fmaxf(m[1], fmaxf(fmaxf(s[2], s[3]), fmaxf(s[6], s[7])));
}
__device__ __forceinline__ void exp_pv(float (&o)[8], float (&sum)[2], const float (&mc)[2], const float (&s)[8],
                                       uint32_t v0, uint32_t v1, uint32_t v2, uint32_t v3) {
  const float C = 0.25f * 1.4426950408889634f;
  float p0 = ex2(fmaf(s[0], C, mc[0])), p1 = ex2(fmaf(s[1], C, mc[0]));
  float p2 = ex2(fmaf(s[2], C, mc[1])), p3 = ex2(fmaf(s[3], C, mc[1]));
  float p4 = ex2(fmaf(s[4], C, mc[0])), p5 = ex2(fmaf(s[5], C, mc[0]));
  float p6 = ex2(fmaf(s[6], C, mc[1])), p7 = ex2(fmaf(s[7], C, mc[1]));
  sum[0] += (p0 + p1) + (p4 + p5);
  sum[1] += (p2 + p3) + (p6 + p7);
  uint32_t a0 = pack_bf16(p0, p1), a1 = pack_bf16(p2, p3), a2 = pack_bf16(p4, p5), a3 = pack_bf16(p6, p7);
  mma16816(&o[0], a0, a1, a2, a3, v0, v1);
  mma16816(&o[4], a0, a1, a2, a3, v2, v3);
}
template <int MA, int MB>
__device__ __forceinline__ void max2(float (&mA)[2], float (&mB)[2], const uint32_t (&qA)[4], const uint32_t (&qB)[4], uint32_t kaddr, int lane) {
  uint32_t k0, k1, k2, k3;
  ldmatrix_x4(kaddr, k0, k1, k2, k3);
  if (MA >= 0) { float s[8]; qk_frag<MA>(s, qA, k0, k1, k2, k3, lane); upd_max(mA, s); }
  if (MB >= 0) { float s[8]; qk_frag<MB>(s, qB, k0, k1, k2, k3, lane); upd_max(mB, s); }
}
template <int MA, int MB>
__device__ __forceinline__ void exp2t(float (&oA)[8], float (&oB)[8], float (&sA)[2], float (&sB)[2], const float (&mA)[2], const float (&mB)[2],
                                      const uint32_t (&qA)[4], const uint32_t (&qB)[4], uint32_t kaddr, uint32_t vaddr, int lane) {
  uint32_t k0, k1, k2, k3, v0, v1, v2, v3;
  ldmatrix_x4(kaddr, k0, k1, k2, k3);
  ldmatrix_x4_t(vaddr, v0, v1, v2, v3);
  if (MA >= 0) { float s[8]; qk_frag<MA>(s, qA, k0, k1, k2, k3, lane); exp_pv(oA, sA, mA, s, v0, v1, v2, v3); }
  if (MB >= 0) { float s[8]; qk_frag<MB>(s, qB, k0, k1, k2, k3, lane); exp_pv(oB, sB, mB, s, v0, v1, v2, v3); }
}
__device__ __forceinline__ void bound_shift(float (&mc)[2], const uint32_t (&q)[4], float k2max) {
  const float C = 0.25f * 1.4426950408889634f;
  float n0 = bf_lo(q[0]) * bf_lo(q[0]) + bf_hi(q[0]) * bf_hi(q[0]) + bf_lo(q[2]) * bf_lo(q[2]) + bf_hi(q[2]) * bf_hi(q[2]);
  float n1 = bf_lo(q[1]) * bf_lo(q[1]) + bf_hi(q[1]) * bf_hi(q[1]) + bf_lo(q[3]) * bf_lo(q[3]) + bf_hi(q[3]) * bf_hi(q[3]);
  n0 += __shfl_xor_sync(0xffffffffu, n0, 1); n0 += __shfl_xor_sync(0xffffffffu, n0, 2);
  n1 += __shfl_xor_sync(0xffffffffu, n1, 1); n1 += __shfl_xor_sync(0xffffffffu, n1, 2);
  mc[0] = -sqrtf(n0 * k2max) * (1.001f * C);
  mc[1] = -sqrtf(n1 * k2max) * (1.001f * C);
}
__device__ __forceinline__ bool sums_ok(float (&s)[2]) {
  s[0] += __shfl_xor_sync(0xffffffffu, s[0], 1); s[0] += __shfl_xor_sync(0xffffffffu, s[0], 2);
  s[1] += __shfl_xor_sync(0xffffffffu, s[1], 1); s[1] += __shfl_xor_sync(0xffffffffu, s[1], 2);
  return (s[0] >= 8.0779e-28f) && (s[1] >= 8.0779e-28f) && (s[0] <= 1e30f) && (s[1] <= 1e30f);
}
__device__ __forceinline__ void attention_pair(uint32_t sm, int t, int h, int lane, int lo, float k2max) {
  const uint32_t Qb = sm + SM_X + 2 * 16384;
  const int l7 = lane & 7;
  uint32_t qA[4], qB[4];
  const int rowq = 16 * t + l7 + ((lane >> 3) & 1) * 8;
  const uint32_t qa = Qb + rowq * 128 + (((2 * h + (lane >> 4)) ^ l7) << 4);
  ldmatrix_x4(qa, qA[0], qA[1], qA[2], qA[3]);
  ldmatrix_x4(qa + 2048, qB[0], qB[1], qB[2], qB[3]);
  const uint32_t ko = (uint32_t)((l7 + ((lane >> 4) & 1) * 8) * 128 + (((2 * h + ((lane >> 3) & 1)) ^ l7) << 4));
  const uint32_t vo = (uint32_t)((l7 + ((lane >> 3) & 1) * 8) * 128 + (((2 * h + (lane >> 4)) ^ l7) << 4));
  const int b0 = (t + 2 > lo) ? t + 2 : lo;
  float mA[2], mB[2];
  bound_shift(mA, qA, k2max);
  bound_shift(mB, qB, k2max);
  float oA[8], oB[8], sA[2], sB[2];
#pragma unroll 1
  for (int attempt = 0; attempt < 2; attempt++) {
    if (attempt) {
      mA[0] = mA[1] = mB[0] = mB[1] = -INFINITY;
      if (t >= lo) max2<1, -1>(mA, mB, qA, qB, KBLK(sm, t) + ko, lane);
      if (t + 1 >= lo) max2<0, 1>(mA, mB, qA, qB, KBLK(sm, t + 1) + ko, lane);
#pragma unroll 1
      for (int blk = b0; blk < t + 16; blk++) max2<0, 0>(mA, mB, qA, qB, KBLK(sm, blk) + ko, lane);
      max2<2, 0>(mA, mB, qA, qB, KBLK(sm, t + 16) + ko, lane);
      max2<-1, 2>(mA, mB, qA, qB, KBLK(sm, t + 17) + ko, lane);
      finish_max(mA);
      finish_max(mB);
    }
    sA[0] = sA[1] = sB[0] = sB[1] = 0.f;
#pragma unroll
    for (int i = 0; i < 8; i++) { oA[i] = 0.f; oB[i] = 0.f; }
    if (t >= lo) exp2t<1, -1>(oA, oB, sA, sB, mA, mB, qA, qB, KBLK(sm, t) + ko, VBLK(sm, t) + vo, lane);
    if (t + 1 >= lo) exp2t<0, 1>(oA, oB, sA, sB, mA, mB, qA, qB, KBLK(sm, t + 1) + ko, VBLK(sm, t + 1) + vo, lane);
    {
      float cA[8], cB[8];
      {
        uint32_t k0, k1, k2, k3;
        ldmatrix_x4(KBLK(sm, b0) + ko, k0, k1, k2, k3);
        qk_frag<0>(cA, qA, k0, k1, k2, k3, lane);
        qk_frag<0>(cB, qB, k0, k1, k2, k3, lane);
      }
#pragma unroll 2
      for (int blk = b0; blk < t + 16; blk++) {
        float nA[8], nB[8];
        uint32_t k0, k1, k2, k3, v0, v1, v2, v3;
        ldmatrix_x4(KBLK(sm, blk + 1) + ko, k0, k1, k2, k3);
        ldmatrix_x4_t(VBLK(sm, blk) + vo, v0, v1, v2, v3);
        qk_frag<0>(nA, qA, k0, k1, k2, k3, lane);
        qk_frag<0>(nB, qB, k0, k1, k2, k3, lane);
        exp_pv(oA, sA, mA, cA, v0, v1, v2, v3);
        exp_pv(oB, sB, mB, cB, v0, v1, v2, v3);
#pragma unroll
        for (int i = 0; i < 8; i++) { cA[i] = nA[i]; cB[i] = nB[i]; }
      }
    }
    exp2t<2, 0>(oA, oB, sA, sB, mA, mB, qA, qB, KBLK(sm, t + 16) + ko, VBLK(sm, t + 16) + vo, lane);
    exp2t<-1, 2>(oA, oB, sA, sB, mA, mB, qA, qB, KBLK(sm, t + 17) + ko, VBLK(sm, t + 17) + vo, lane);
    const bool okA = sums_ok(sA), okB = sums_ok(sB);
    if (__all_sync(0xffffffffu, okA && okB)) break;
  }
  store_o(Qb, t, h, lane, oA, sA);
  store_o(Qb, t + 1, h, lane, oB, sB);
}
__device__ __forceinline__ void attention_one(uint32_t sm, int t, int h, int lane, int lo, float k2max) {
  const uint32_t Qb = sm + SM_X + 2 * 16384;
  const int l7 = lane & 7;
  uint32_t qA[4];
  const int rowq = 16 * t + l7 + ((lane >> 3) & 1) * 8;
  ldmatrix_x4(Qb + rowq * 128 + (((2 * h + (lane >> 4)) ^ l7) << 4), qA[0], qA[1], qA[2], qA[3]);
  const uint32_t ko = (uint32_t)((l7 + ((lane >> 4) & 1) * 8) * 128 + (((2 * h + ((lane >> 3) & 1)) ^ l7) << 4));
  const uint32_t vo = (uint32_t)((l7 + ((lane >> 3) & 1) * 8) * 128 + (((2 * h + (lane >> 4)) ^ l7) << 4));
  const int b0 = (t + 1 > lo) ? t + 1 : lo;
  float mA[2];
  bound_shift(mA, qA, k2max);
  float oA[8], sA[2];
#pragma unroll 1
  for (int attempt = 0; attempt < 2; attempt++) {
    if (attempt) {
      mA[0] = mA[1] = -INFINITY;
      if (t >= lo) max2<1, -1>(mA, mA, qA, qA, KBLK(sm, t) + ko, lane);
#pragma unroll 1
      for (int blk = b0; blk < t + 16; blk++) max2<0, -1>(mA, mA, qA, qA, KBLK(sm, blk) + ko, lane);
      max2<2, -1>(mA, mA, qA, qA, KBLK(sm, t + 16) + ko, lane);
      finish_max(mA);
    }
    sA[0] = sA[1] = 0.f;
#pragma unroll
    for (int i = 0; i < 8; i++) oA[i] = 0.f;
    if (t >= lo) exp2t<1, -1>(oA, oA, sA, sA, mA, mA, qA, qA, KBLK(sm, t) + ko, VBLK(sm, t) + vo, lane);
#pragma unroll 2
    for (int blk = b0; blk < t + 16; blk++) exp2t<0, -1>(oA, oA, sA, sA, mA, mA, qA, qA, KBLK(sm, blk) + ko, VBLK(sm, blk) + vo, lane);
    exp2t<2, -1>(oA, oA, sA, sA, mA, mA, qA, qA, KBLK(sm, t + 16) + ko, VBLK(sm, t + 16) + vo, lane);
    const bool okA = sums_ok(sA);
    if (__all_sync(0xffffffffu, okA)) break;
  }
  store_o(Qb, t, h, lane, oA, sA);
}
template <int T0>
__device__ __forceinline__ void stage_h(const uint32_t (&h)[44], uint32_t sm, int w, int warp, int lane) {
  const int row = warp * 16 + (lane & 7) + ((lane >> 3) & 1) * 8;
  uint32_t addr;
  if (T0 < 16) {
    int ch = (T0 & 7) + (lane >> 4);
    addr = sm + SM_RING + (T0 >> 3) * 16384 + w * 8192 + row * 128 + ((ch ^ (row & 7)) << 4);
  } else {
    addr = sm + SM_RING + 2 * 16384 + w * 8192 + (uint32_t)(((T0 >= 16 ? T0 : 16) - 16) >> 1) * 2048u + row * 32 + (lane >> 4) * 16;
  }
  stmatrix_x4(addr, h[2 * T0], h[2 * T0 + 1], h[2 * T0 + 2], h[2 * T0 + 3]);
}
__device__ __forceinline__ uint32_t mish2(float h0, float h1) {
  const float e0 = ex2(fminf(h0, 20.0f) * 1.4426950408889634f), e1 = ex2(fminf(h1, 20.0f) * 1.4426950408889634f);
  const float n0 = e0 * (e0 + 2.0f), n1 = e1 * (e1 + 2.0f);
  const float d0 = n0 + 2.0f, d1 = n1 + 2.0f;
  const float r = rcp(d0 * d1);
  return pack_bf16(h0 * n0 * (r * d1), h1 * n1 * (r * d0));
}

__device__ __forceinline__ void mish_all(uint8_t* smem_raw, uint32_t bar0, int tl) {
  mbar_wait(bar0 + 8u * (uint32_t)B_HST, 0);
#pragma unroll 1
  for (int idx = tl; idx < 2816; idx += 224) {
    uint32_t off; int col;
    if (idx < 2048) {
      const int row = (idx >> 3) & 127, pch = idx & 7;
      off = (uint32_t)idx * 16u;
      col = (idx >> 10) * 64 + ((pch ^ (row & 7)) << 3);
    } else {
      const int id2 = idx - 2048;
      const int w = id2 >= 384 ? 1 : 0, rem = id2 - w * 384;
      off = 2u * 16384u + (uint32_t)w * 8192u + (uint32_t)rem * 16u;
      col = 128 + (rem >> 7) * 16 + (rem & 1) * 8;
    }
    uint4 v = *reinterpret_cast<const uint4*>(smem_raw + SM_RING + off);
    const float4 ba = *reinterpret_cast<const float4*>(smem_raw + SM_B1 + col * 4);
    const float4 bb = *reinterpret_cast<const float4*>(smem_raw + SM_B1 + col * 4 + 16);
    v.x = mish2(bf_lo(v.x) + ba.x, bf_hi(v.x) + ba.y);
    v.y = mish2(bf_lo(v.y) + ba.z, bf_hi(v.y) + ba.w);
    v.z = mish2(bf_lo(v.z) + bb.x, bf_hi(v.z) + bb.y);
    v.w = mish2(bf_lo(v.w) + bb.z, bf_hi(v.w) + bb.w);
    *reinterpret_cast<uint4*>(smem_raw + SM_RING + off) = v;
  }
  fence_proxy_async_smem();
  mbar_arrive(bar0 + 8u * (uint32_t)B_ACTDONE);
}

__global__ void __launch_bounds__(512, 1)
fused_kernel(const __grid_constant__ CUtensorMap tm_x, const __grid_constant__ CUtensorMap tm_wqkv,
             const __grid_constant__ CUtensorMap tm_w1, const __grid_constant__ CUtensorMap tm_w2,
             const __grid_constant__ CUtensorMap tm_wo, const __grid_constant__ CUtensorMap tm_kvo,
             const __grid_constant__ CUtensorMap tm_act, const __grid_constant__ CUtensorMap tm_act_st,
             const __grid_constant__ CUtensorMap tm_act_tail, const __grid_constant__ CUtensorMap tm_out,
             const bf16* __restrict__ gate_w, const bf16* __restrict__ b1,
             const bf16* __restrict__ gx, const bf16* __restrict__ gw1, const bf16* __restrict__ gwqkv,
             const bf16* __restrict__ gw2, const bf16* __restrict__ gwo) {
  extern __shared__ __align__(1024) uint8_t smem_raw[];
  const uint32_t sm = smem_u32(smem_raw);
  const int tid = threadIdx.x, warp_id = tid >> 5, lane = tid & 31, wg = tid >> 7;
  const int rb = blockIdx.x >> 3, j = blockIdx.x & 7;
  const uint32_t bar0 = sm + SM_BAR;
  auto BAR = [&](int i) { return bar0 + 8u * (uint32_t)i; };

  if (tid == 448) {
    const int c = blockIdx.x;
    l2_prefetch(reinterpret_cast<const uint8_t*>(gwqkv) + c * 12288, 12288);
    l2_prefetch(reinterpret_cast<const uint8_t*>(gx) + c * 16384, 16384);
    l2_prefetch(reinterpret_cast<const uint8_t*>(gw1) + c * 11008, 11008);
    l2_prefetch(reinterpret_cast<const uint8_t*>(gw2) + c * 11008, 11008);
    l2_prefetch(reinterpret_cast<const uint8_t*>(gwo) + c * 4096, 4096);
  }
  if (tid == 0) {
    if (sm & 1023) __trap();
    for (int i = 0; i < 8; i++) { mbar_init(BAR(B_XFULL + i), 1); mbar_init(BAR(B_OFULL + i), 1); }
    for (int i = 0; i < 4; i++) {
      mbar_init(BAR(B_WFULL + i), 1);
      mbar_init(BAR(B_WEMPTY + i), 2);
      mbar_init(BAR(B_DFULL + i), 1);
    }
    mbar_init(BAR(B_GATE), 128);
    mbar_init(BAR(B_HST), 256);
    mbar_init(BAR(B_KVST), 256);
    mbar_init(BAR(B_XFREE), 2);
    mbar_init(BAR(B_QKVST), 256);
    mbar_init(BAR(B_ACTDONE), 224);
    mbar_init(BAR(B_KVFULL), 3);
    mbar_init(BAR(B_OST), 384);
    mbar_init(BAR(B_WOFULL), 1);
    *reinterpret_cast<unsigned*>(smem_raw + SM_CTR) = 0u;
    for (int i = 0; i < 4; i++) reinterpret_cast<unsigned*>(smem_raw + SM_KN)[i] = 0u;
    asm volatile("fence.mbarrier_init.release.cluster;" ::: "memory");
  }
  __syncthreads();
  const unsigned epoch1 = *((volatile unsigned*)&g_epoch) + 1u;
  if (tid == 0) TS(0);

  if (wg == 3) {
    asm volatile("setmaxnreg.dec.sync.aligned.u32 40;");
    if (warp_id == 12) {
      if (lane == 0) {
        const int c0 = chunk_start(j);
        for (int it = 0; it < 16; it++) {
          const int st = it & 3, kb = it & 7;
          if (it < 4) {
            mbar_expect_tx(BAR(B_XFULL + it), 16384);
            tma_load_2d(sm + SM_X + it * 16384, &tm_x, it * 64, rb * 128, BAR(B_XFULL + it));
          }
          if (it == 4) {
            for (int i = 4; i < 8; i++) {
              mbar_expect_tx(BAR(B_XFULL + i), 16384);
              tma_load_2d(sm + SM_X + i * 16384, &tm_x, i * 64, rb * 128, BAR(B_XFULL + i));
            }
          }
          if (it >= 4) mbar_wait(BAR(B_WEMPTY + st), ((it >> 2) - 1) & 1);
          mbar_expect_tx(BAR(B_WFULL + st), 24576);
          const uint32_t dst = sm + SM_RING + st * STAGE_BYTES;
          if (it >= 8) {
            for (int b = 0; b < 3; b++) tma_load_2d(dst + b * 8192, &tm_w1, c0 + b * 64, kb * 64, BAR(B_WFULL + st));
          } else {
            for (int b = 0; b < 3; b++) tma_load_2d(dst + b * 8192, &tm_wqkv, b * 512 + j * 64, kb * 64, BAR(B_WFULL + st));
          }
        }
        prefetch_tm(&tm_act); prefetch_tm(&tm_w2); prefetch_tm(&tm_wo); prefetch_tm(&tm_out); prefetch_tm(&tm_act_st); prefetch_tm(&tm_act_tail);
      }
    } else if (warp_id == 13) {
      float4 kn = make_float4(0.f, 0.f, 0.f, 0.f);
      if (lane == 0) {
        prefetch_tm(&tm_wqkv); prefetch_tm(&tm_kvo);
        mbar_wait(BAR(B_KVST), 0);
        tma_store_2d(&tm_kvo, sm + SM_X + 0 * 16384, j * 64, rb * 128);
        tma_store_2d(&tm_kvo, sm + SM_X + 1 * 16384, 512 + j * 64, rb * 128);
        bulk_commit();
        kn = *reinterpret_cast<const float4*>(smem_raw + SM_KN);
        *reinterpret_cast<float4*>(&g_knorm[(rb * 8 + j) * 4]) = kn;
        bulk_wait0();
        fence_proxy_async();
        st_release(&g_kvflag[rb * 8 + j], epoch1);
        TS(15);
        mbar_wait(BAR(B_XFREE), 0);
      }
      __syncwarp();
      unsigned pending = 6u;
      for (unsigned tries = 0; pending && tries < (1u << 22); tries++) {
        bool rdy = false;
        if ((pending >> lane) & 1u) {
          rdy = (rb < lane) || (int)(ld_acquire(&g_kvflag[(rb - lane) * 8 + j]) - epoch1) >= 0;
          if (rdy && rb >= lane) kn = __ldcg(reinterpret_cast<const float4*>(&g_knorm[((rb - lane) * 8 + j) * 4]));
        }
        const unsigned ready = __ballot_sync(0xffffffffu, rdy);
        if (ready) {
          if (lane == 0) {
            fence_proxy_async();
            for (int d = 1; d <= 2; d++) {
              if ((ready >> d) & 1u) {
                mbar_expect_tx(BAR(B_KVFULL), 32768);
                tma_load_2d(sm + SM_X + (2 + d) * 16384, &tm_kvo, j * 64, (rb - d) * 128, BAR(B_KVFULL));
                tma_load_2d(sm + SM_X + (4 + d) * 16384, &tm_kvo, 512 + j * 64, (rb - d) * 128, BAR(B_KVFULL));
              }
            }
          }
          pending &= ~ready;
          __syncwarp();
        } else {
          __nanosleep(20);
        }
      }
      {
        unsigned m0 = lane < 3 ? __float_as_uint(kn.x) : 0u, m1 = lane < 3 ? __float_as_uint(kn.y) : 0u;
        unsigned m2 = lane < 3 ? __float_as_uint(kn.z) : 0u, m3 = lane < 3 ? __float_as_uint(kn.w) : 0u;
        m0 = __reduce_max_sync(0xffffffffu, m0); m1 = __reduce_max_sync(0xffffffffu, m1);
        m2 = __reduce_max_sync(0xffffffffu, m2); m3 = __reduce_max_sync(0xffffffffu, m3);
        if (lane == 0) {
          *reinterpret_cast<uint4*>(smem_raw + SM_KN + 16) = make_uint4(m0, m1, m2, m3);
          mbar_arrive(BAR(B_KVFULL));
        }
      }
    }
    __syncwarp();
    mbar_wait(BAR(B_QKVST), 0);
    asm volatile("setmaxnreg.inc.sync.aligned.u32 120;");
  } else {
    if (wg == 2) {
      asm volatile("setmaxnreg.dec.sync.aligned.u32 80;");
      const int tl = tid - 256;
      {
        float* b1s = reinterpret_cast<float*>(smem_raw + SM_B1);
        const int c0 = chunk_start(j);
        for (int i = tl; i < 176; i += 128) b1s[i] = (c0 + i < FF) ? __bfloat162float(b1[c0 + i]) : 0.f;
      }
      {
        const int row = j * 16 + (tl >> 3), kb = tl & 7;
        uint4 gv[8];
#pragma unroll
        for (int ch = 0; ch < 8; ch++) gv[ch] = __ldg(reinterpret_cast<const uint4*>(gate_w + kb * 64 + ch * 8));
        mbar_wait(BAR(B_XFULL + kb), 0);
        float a0 = 0.f, a1 = 0.f;
#pragma unroll
        for (int ch = 0; ch < 8; ch++) {
          uint4 v = *reinterpret_cast<const uint4*>(smem_raw + SM_X + kb * 16384 + row * 128 + ((ch ^ (row & 7)) << 4));
          const uint32_t* pv = reinterpret_cast<const uint32_t*>(&v);
          const uint32_t* pg = reinterpret_cast<const uint32_t*>(&gv[ch]);
#pragma unroll
          for (int e = 0; e < 4; e++) {
            const uint32_t pr = pack_bf16(bf_lo(pv[e]) * bf_lo(pg[e]), bf_hi(pv[e]) * bf_hi(pg[e]));
            a0 += bf_lo(pr);
            a1 += bf_hi(pr);
          }
        }
        mbar_arrive(BAR(B_GATE));
        float acc = a0 + a1;
        acc += __shfl_xor_sync(0xffffffffu, acc, 1);
        acc += __shfl_xor_sync(0xffffffffu, acc, 2);
        acc += __shfl_xor_sync(0xffffffffu, acc, 4);
        if ((tl & 7) == 0) {
          float sb = bf16r(acc);
          g_gate[rb * 128 + row] = bf16r(1.0f / (1.0f + __expf(-sb)));
        }
        __threadfence();
        named_bar_sync(3, 128);
        if (tl == 0) { red_release_add(&g_actcnt[rb], 1u); TS(6); }
      }
      mbar_wait(BAR(B_QKVST), 0);
      asm volatile("setmaxnreg.inc.sync.aligned.u32 120;");
    } else {
      asm volatile("setmaxnreg.inc.sync.aligned.u32 192;");
      const int w = wg, warp = warp_id & 3;
      const bool elect = (tid & 127) == 0;
      {
        uint32_t qp[48];
        const uint32_t xa = sm + SM_X + w * 8192;
        {
          float qacc[96];
#pragma unroll 1
          for (int kb = 0; kb < 8; kb++) {
            const int st = kb & 3;
            mbar_wait(BAR(B_XFULL + kb), 0);
            mbar_wait(BAR(B_WFULL + st), (kb >> 2) & 1);
            if (tid == 0 && !(kb & 1)) TS(28 + (kb >> 1));
            wgmma_fence();
#pragma unroll
            for (int ks = 0; ks < 4; ks++)
              wgmma_n192(qacc, desc_kmajor(xa + kb * 16384 + ks * 32), desc_mnmajor(sm + SM_RING + st * STAGE_BYTES + ks * 2048), (kb | ks) != 0);
            wgmma_commit();
            wgmma_wait<1>();
            if (elect && kb > 0) mbar_arrive(BAR(B_WEMPTY + ((kb - 1) & 3)));
          }
          wgmma_wait<0>();
          if (elect) mbar_arrive(BAR(B_WEMPTY + 3));
          if (tid == 0) TS(7);
#pragma unroll
          for (int i = 0; i < 48; i++) qp[i] = pack_bf16(qacc[2 * i], qacc[2 * i + 1]);
        }
        const int srow = w * 64 + warp * 16 + (lane & 7) + ((lane >> 3) & 1) * 8;
        const uint32_t rbase = sm + SM_X + srow * 128;
        float hacc[88];
#pragma unroll 1
        for (int kb = 0; kb < 8; kb++) {
          const int st = kb & 3;
          mbar_wait(BAR(B_WFULL + st), (kb >> 2) & 1);
          if (tid == 0) TS(18 + kb);
          wgmma_fence();
#pragma unroll
          for (int ks = 0; ks < 4; ks++)
            wgmma_n176(hacc, desc_kmajor(xa + kb * 16384 + ks * 32), desc_mnmajor(sm + SM_RING + st * STAGE_BYTES + ks * 2048), (kb | ks) != 0);
          wgmma_commit();
          wgmma_wait<1>();
          if (elect && kb > 0) mbar_arrive(BAR(B_WEMPTY + ((kb - 1) & 3)));
          if (kb == 1) {
            mbar_wait(BAR(B_GATE), 0);
#pragma unroll
            for (int nt = 0; nt < 8; nt += 2)
              stmatrix_x4(rbase + 0 * 16384 + (((nt + (lane >> 4)) ^ (srow & 7)) << 4), qp[16 + 2 * nt], qp[17 + 2 * nt], qp[18 + 2 * nt], qp[19 + 2 * nt]);
#pragma unroll
            for (int hh = 0; hh < 4; hh++) {
              const uint32_t a0 = qp[16 + 4 * hh], a1 = qp[17 + 4 * hh], b0 = qp[18 + 4 * hh], b1 = qp[19 + 4 * hh];
              float n0 = bf_lo(a0) * bf_lo(a0) + bf_hi(a0) * bf_hi(a0) + bf_lo(b0) * bf_lo(b0) + bf_hi(b0) * bf_hi(b0);
              float n1 = bf_lo(a1) * bf_lo(a1) + bf_hi(a1) * bf_hi(a1) + bf_lo(b1) * bf_lo(b1) + bf_hi(b1) * bf_hi(b1);
              n0 += __shfl_xor_sync(0xffffffffu, n0, 1); n0 += __shfl_xor_sync(0xffffffffu, n0, 2);
              n1 += __shfl_xor_sync(0xffffffffu, n1, 1); n1 += __shfl_xor_sync(0xffffffffu, n1, 2);
              float n = fmaxf(n0, n1);
              n = fmaxf(n, __shfl_xor_sync(0xffffffffu, n, 4));
              n = fmaxf(n, __shfl_xor_sync(0xffffffffu, n, 8));
              n = fmaxf(n, __shfl_xor_sync(0xffffffffu, n, 16));
              if (lane == 0) atomicMax(reinterpret_cast<unsigned*>(smem_raw + SM_KN) + hh, __float_as_uint(n));
            }
          } else if (kb == 2) {
#pragma unroll
            for (int nt = 0; nt < 8; nt += 2)
              stmatrix_x4(rbase + 1 * 16384 + (((nt + (lane >> 4)) ^ (srow & 7)) << 4), qp[32 + 2 * nt], qp[33 + 2 * nt], qp[34 + 2 * nt], qp[35 + 2 * nt]);
            fence_proxy_async_smem();
            mbar_arrive(BAR(B_KVST));
          } else if (kb == 3) {
#pragma unroll
            for (int nt = 0; nt < 8; nt += 2)
              stmatrix_x4(rbase + 2 * 16384 + (((nt + (lane >> 4)) ^ (srow & 7)) << 4), qp[2 * nt], qp[1 + 2 * nt], qp[2 + 2 * nt], qp[3 + 2 * nt]);
            if (tid == 0) TS(17);
          } else if (kb == 7) {
            if (elect) mbar_arrive(BAR(B_XFREE));
          }
        }
        wgmma_wait<0>();
        if (elect) mbar_arrive(BAR(B_WEMPTY + 3));
        if (tid == 0) TS(8);
        {
          uint32_t hp[44];
#pragma unroll
          for (int i = 0; i < 44; i++) hp[i] = pack_bf16(hacc[2 * i], hacc[2 * i + 1]);
          mbar_wait(BAR(B_WEMPTY + 0), 1);
          mbar_wait(BAR(B_WEMPTY + 1), 1);
          stage_h<0>(hp, sm, w, warp, lane); stage_h<2>(hp, sm, w, warp, lane); stage_h<4>(hp, sm, w, warp, lane); stage_h<6>(hp, sm, w, warp, lane);
          stage_h<8>(hp, sm, w, warp, lane); stage_h<10>(hp, sm, w, warp, lane); stage_h<12>(hp, sm, w, warp, lane); stage_h<14>(hp, sm, w, warp, lane);
          stage_h<16>(hp, sm, w, warp, lane); stage_h<18>(hp, sm, w, warp, lane); stage_h<20>(hp, sm, w, warp, lane);
        }
        mbar_arrive(BAR(B_HST));
        mbar_arrive(BAR(B_QKVST));
      }
      asm volatile("setmaxnreg.dec.sync.aligned.u32 120;");
    }
  }
  if (wg >= 2 && warp_id != 13) mish_all(smem_raw, bar0, tid < 416 ? tid - 256 : tid - 288);
  if (wg == 3) {
    const int warp = warp_id & 3;
    const bool elect = (tid & 127) == 0;
    auto load_stage = [&](int it) {
      const int st = it & 3;
      const uint32_t dst = sm + SM_RING + st * STAGE_BYTES;
      mbar_expect_tx(BAR(B_DFULL + st), 24576);
      tma_load_2d(dst, &tm_act, it * 64, rb * 128, BAR(B_DFULL + st));
      tma_load_2d(dst + 16384, &tm_w2, j * 64, it * 64, BAR(B_DFULL + st));
    };
    float* gs = reinterpret_cast<float*>(smem_raw + SM_B1);
    if (elect) {
      const int c0 = chunk_start(j), ntail = (chunk_len(j) - 128) >> 4;
      mbar_wait(BAR(B_ACTDONE), 0);
      TS(16);
      for (int w = 0; w < 2; w++) {
        tma_store_2d(&tm_act_st, sm + SM_RING + 0 * 16384 + w * 8192, c0, rb * 128 + w * 64);
        tma_store_2d(&tm_act_st, sm + SM_RING + 1 * 16384 + w * 8192, c0 + 64, rb * 128 + w * 64);
        for (int s = 0; s < ntail; s++)
          tma_store_2d(&tm_act_tail, sm + SM_RING + 2 * 16384 + w * 8192 + s * 2048, c0 + 128 + s * 16, rb * 128 + w * 64);
      }
      bulk_commit();
      bulk_wait0();
      fence_proxy_async();
      red_release_add(&g_actcnt[rb], 1u);
      TS(14);
      TS(1);
      spin_ge(&g_actcnt[rb], epoch1 * 16u);
      TS(2);
      fence_proxy_async();
      for (int it = 0; it < 4; it++) load_stage(it);
    }
    const uint32_t ob = sm + SM_RING;
    const uint32_t oaddr = ob + ((lane & 7) + (lane >> 4) * 8) * 128;
    const uint32_t ochunk = (uint32_t)(2 * warp + ((lane >> 3) & 1));
    {
      float acc[64];
#pragma unroll 1
      for (int it = 0; it < 22; it++) {
        const int st = it & 3;
        const uint32_t sb = sm + SM_RING + st * STAGE_BYTES;
        mbar_wait(BAR(B_DFULL + st), (it >> 2) & 1);
        wgmma_fence();
#pragma unroll
        for (int ks = 0; ks < 4; ks++)
          wgmma_n128_ta(acc, desc_mnmajor(sb + 16384 + ks * 2048), desc_kmajor(sb + ks * 32), (it | ks) != 0);
        wgmma_commit();
        wgmma_wait<1>();
        if (it > 0 && it + 3 < 22) {
          named_bar_sync(2, 128);
          if (elect) load_stage(it + 3);
        }
      }
      wgmma_wait<0>();
      named_bar_sync(2, 128);
      if (elect) {
        mbar_expect_tx(BAR(B_WOFULL), 65536);
        for (int kb = 0; kb < 8; kb++) tma_load_2d(sm + SM_RING + 16384 + kb * 8192, &tm_wo, j * 64, kb * 64, BAR(B_WOFULL));
      }
      if (tid - 384 < 64) {
        const float2 g2 = __ldcg(reinterpret_cast<const float2*>(&g_gate[rb * 128 + 2 * (tid - 384)]));
        reinterpret_cast<uint2*>(gs)[tid - 384] = make_uint2(pack_bf16(g2.x, g2.y), pack_bf16(1.0f - g2.x, 1.0f - g2.y));
      }
#pragma unroll
      for (int nt = 0; nt < 16; nt += 2)
        stmatrix_x4_t(oaddr + nt * 1024 + ((ochunk ^ (lane & 7)) << 4),
                      pack_bf16(acc[4 * nt], acc[4 * nt + 1]), pack_bf16(acc[4 * nt + 2], acc[4 * nt + 3]),
                      pack_bf16(acc[4 * nt + 4], acc[4 * nt + 5]), pack_bf16(acc[4 * nt + 6], acc[4 * nt + 7]));
    }
    if (tid == 384) TS(11);
    named_bar_sync(2, 128);
    float acc[64];
    mbar_wait(BAR(B_WOFULL), 0);
    mbar_wait(BAR(B_OST), 0);
#pragma unroll 1
    for (int i = 0; i < 8; i++) {
      const int kb = (j + i) & 7;
      const uint32_t ab = sm + SM_X + (i == 0 ? 2u : (i < 3 ? (uint32_t)(i - 1) : (uint32_t)i)) * 16384u;
      const uint32_t bb = sm + SM_RING + 16384 + kb * 8192;
      if (i > 0) mbar_wait(BAR(B_OFULL + i), 0);
      wgmma_fence();
#pragma unroll
      for (int ks = 0; ks < 4; ks++)
        wgmma_n128_ta(acc, desc_mnmajor(bb + ks * 2048), desc_kmajor(ab + ks * 32), (i | ks) != 0);
      wgmma_commit();
      wgmma_wait<1>();
    }
    wgmma_wait<0>();
    if (tid == 384) TS(12);
#pragma unroll
    for (int nt = 0; nt < 16; nt += 2) {
      const uint32_t a = oaddr + nt * 1024 + ((ochunk ^ (lane & 7)) << 4);
      uint32_t pk[4];
      ldmatrix_x4_t(a, pk[0], pk[1], pk[2], pk[3]);
      const uint2 gq0 = *reinterpret_cast<const uint2*>(&gs[8 * nt + 2 * (lane & 3)]);
      const uint2 gq1 = *reinterpret_cast<const uint2*>(&gs[8 * nt + 8 + 2 * (lane & 3)]);
      uint32_t r[4];
#pragma unroll
      for (int i = 0; i < 4; i++) {
        const uint32_t av = pack_bf16(acc[4 * nt + 2 * i], acc[4 * nt + 2 * i + 1]);
        const uint2 gq = (i & 2) ? gq1 : gq0;
        const __nv_bfloat162 t1 = __hmul2(*reinterpret_cast<const __nv_bfloat162*>(&gq.x), *reinterpret_cast<const __nv_bfloat162*>(&av));
        const __nv_bfloat162 t2 = __hmul2(*reinterpret_cast<const __nv_bfloat162*>(&gq.y), *reinterpret_cast<const __nv_bfloat162*>(&pk[i]));
        const __nv_bfloat162 t3 = __hadd2(t1, t2);
        r[i] = *reinterpret_cast<const uint32_t*>(&t3);
      }
      stmatrix_x4_t(a, r[0], r[1], r[2], r[3]);
    }
    fence_proxy_async_smem();
    named_bar_sync(1, 128);
    if (elect) {
      tma_store_2d(&tm_out, ob, j * 64, rb * 128);
      bulk_commit();
      asm volatile("cp.async.bulk.wait_group.read 0;" ::: "memory");
    }
  } else {
    mbar_wait(BAR(B_QKVST), 0);
    mbar_wait(BAR(B_KVFULL), 0);
    if (tid == 128) TS(9);
    const int lo = rb >= 2 ? 0 : (2 - rb) * 8;
#pragma unroll 1
    while (true) {
      int u = 0;
      if (lane == 0) u = (int)atomicAdd(reinterpret_cast<unsigned*>(smem_raw + SM_CTR), 1u);
      u = __shfl_sync(0xffffffffu, u, 0);
      if (u >= 20) break;
      const float k2max = reinterpret_cast<const float*>(smem_raw + SM_KN + 16)[u < 12 ? (u >> 2) : 3];
      if (u < 12) attention_pair(sm, (u & 3) * 2, u >> 2, lane, lo, k2max);
      else attention_one(sm, 19 - u, 3, lane, lo, k2max);
    }
    if (tid == 128) TS(10);
    fence_proxy_async_smem();
    mbar_arrive(BAR(B_OST));
    if (tid == 0) {
      mbar_wait(BAR(B_OST), 0);
      tma_store_2d(&tm_kvo, sm + SM_X + 2 * 16384, 1024 + j * 64, rb * 128);
      bulk_commit();
      bulk_wait0();
      fence_proxy_async();
      st_release(&g_oflag[rb * 8 + j], epoch1);
      TS(5);
    }
    if (warp_id == 1) {
      mbar_wait(BAR(B_OST), 0);
      if (lane == 0) TS(3);
      unsigned pending = 0xFEu;
      for (unsigned tries = 0; pending && tries < (1u << 22); tries++) {
        bool rdy = false;
        if ((pending >> lane) & 1u) rdy = (int)(ld_acquire(&g_oflag[rb * 8 + ((j + lane) & 7)]) - epoch1) >= 0;
        const unsigned ready = __ballot_sync(0xffffffffu, rdy);
        if (ready) {
          if (lane == 0) {
            fence_proxy_async();
            for (int i = 1; i < 8; i++) {
              if ((ready >> i) & 1u) {
                const int kb = (j + i) & 7;
                mbar_expect_tx(BAR(B_OFULL + i), 16384);
                tma_load_2d(sm + SM_X + (i < 3 ? i - 1 : i) * 16384, &tm_kvo, 1024 + kb * 64, rb * 128, BAR(B_OFULL + i));
              }
            }
          }
          pending &= ~ready;
          __syncwarp();
        } else {
          __nanosleep(20);
        }
      }
      if (lane == 0) TS(4);
    }
  }
  __syncthreads();
  if (tid == 0) {
    TS(13);
    __threadfence();
    unsigned old = atomicAdd(&g_done, 1u);
    if (old == NCTA - 1) {
      g_done = 0;
      __threadfence();
      *((volatile unsigned*)&g_epoch) = epoch1;
    }
  }
}

typedef CUresult (*PFN_encodeTiled)(CUtensorMap*, CUtensorMapDataType, cuuint32_t, void*, const cuuint64_t*, const cuuint64_t*,
                                    const cuuint32_t*, const cuuint32_t*, CUtensorMapInterleave, CUtensorMapSwizzle,
                                    CUtensorMapL2promotion, CUtensorMapFloatOOBfill);

static void make_tm(PFN_encodeTiled enc, CUtensorMap* tm, const void* ptr, uint64_t rows, uint64_t cols, uint32_t box_rows,
                    uint32_t box_cols, bool swz) {
  cuuint64_t dims[2] = {cols, rows};
  cuuint64_t strides[1] = {cols * 2};
  cuuint32_t box[2] = {box_cols, box_rows};
  cuuint32_t es[2] = {1, 1};
  enc(tm, CU_TENSOR_MAP_DATA_TYPE_BFLOAT16, 2, const_cast<void*>(ptr), dims, strides, box, es, CU_TENSOR_MAP_INTERLEAVE_NONE,
      swz ? CU_TENSOR_MAP_SWIZZLE_128B : CU_TENSOR_MAP_SWIZZLE_NONE, CU_TENSOR_MAP_L2_PROMOTION_L2_128B,
      CU_TENSOR_MAP_FLOAT_OOB_FILL_NONE);
}

extern "C" void kernel_launch(void* const* d_in, const int* in_sizes, int n_in, void* d_out, int out_size) {
  const bf16* x = (const bf16*)d_in[0];
  const bf16* wqkv = (const bf16*)d_in[1];
  const bf16* wo = (const bf16*)d_in[2];
  const bf16* w1 = (const bf16*)d_in[4];
  const bf16* b1 = (const bf16*)d_in[5];
  const bf16* w2 = (const bf16*)d_in[6];
  const bf16* gate_w = (const bf16*)d_in[7];

  static PFN_encodeTiled enc = nullptr;
  static void* p_kvo = nullptr;
  static void* p_act = nullptr;
  if (!enc) {
    void* fn = nullptr;
    cudaDriverEntryPointQueryResult qres;
    cudaGetDriverEntryPoint("cuTensorMapEncodeTiled", &fn, cudaEnableDefault, &qres);
    enc = (PFN_encodeTiled)fn;
    cudaGetSymbolAddress(&p_kvo, g_kvo);
    cudaGetSymbolAddress(&p_act, g_act);
    cudaFuncSetAttribute(fused_kernel, cudaFuncAttributeMaxDynamicSharedMemorySize, SM_TOTAL);
  }
  CUtensorMap tm_x, tm_wqkv, tm_w1, tm_w2, tm_wo, tm_kvo, tm_act, tm_act_st, tm_act_tail, tm_out;
  make_tm(enc, &tm_x, x, SEQ, DM, 128, 64, true);
  make_tm(enc, &tm_wqkv, wqkv, DM, 3 * DM, 64, 64, true);
  make_tm(enc, &tm_w1, w1, DM, FF, 64, 64, true);
  make_tm(enc, &tm_w2, w2, FF, DM, 64, 64, true);
  make_tm(enc, &tm_wo, wo, DM, DM, 64, 64, true);
  make_tm(enc, &tm_kvo, p_kvo, SEQ, 1536, 128, 64, true);
  make_tm(enc, &tm_act, p_act, SEQ, FF, 128, 64, true);
  make_tm(enc, &tm_act_st, p_act, SEQ, FF, 64, 64, true);
  make_tm(enc, &tm_act_tail, p_act, SEQ, FF, 64, 16, false);
  make_tm(enc, &tm_out, d_out, SEQ, DM, 128, 64, true);
  fused_kernel<<<NCTA, 512, SM_TOTAL>>>(tm_x, tm_wqkv, tm_w1, tm_w2, tm_wo, tm_kvo, tm_act, tm_act_st, tm_act_tail, tm_out,
                                        gate_w, b1, x, w1, wqkv, w2, wo);
}
```
